```python
import torch

def _softmax(x, axis=-1):
    return torch.softmax(x, dim=axis)
def _gelu(x):
    return torch.nn.functional.gelu(x, approximate="tanh")
def _silu(x):
    return torch.nn.functional.silu(x)
def _sigmoid(x):
    return torch.sigmoid(x)
def _layernorm(x, axis=-1, eps=1e-5):
    m = x.mean(dim=axis, keepdim=True)
    v = x.var(dim=axis, keepdim=True, unbiased=False)
    return (x - m) / torch.sqrt(v + eps)
def _scatter_add(tgt, idx, src, axis=0):
    return tgt.clone().index_add_(axis, idx, src)
def _segment_sum(src, seg, n):
    out = torch.zeros((n,) + src.shape[1:], dtype=src.dtype)
    return out.index_add_(0, seg, src)
def _pad(x, pw):
    flat = tuple(v for pair in reversed(pw) for v in pair)
    return torch.nn.functional.pad(x, flat)

kernel_name = 'gated_mix__linear_attn_block__sliding_block__prompt'

def setup_inputs():

    _w = (lambda a: (lambda t: t.to(torch.bfloat16) if t.is_floating_point() else t)(torch.as_tensor(a)))
    def _A_setup():
        B, S, D = 1, 2048, 512
        return {
            "x": _w((lambda *s: torch.randn(*s, dtype=torch.bfloat16) * 0.05)(B, S, D)),
            "wqkv": _w((lambda *s: torch.randn(*s, dtype=torch.bfloat16) * 1.6)(D, 3 * D)),
            "wo": _w((lambda *s: torch.randn(*s, dtype=torch.bfloat16) * 1.6)(D, D)),
        }
    _A_in = _A_setup()

    def _B_setup():
        B, S, D = 1, 2048, 512
        return {
            "x": _w((lambda *s: torch.randn(*s, dtype=torch.bfloat16) * 0.05)(B, S, D)),
            "wqkv": _w((lambda *s: torch.randn(*s, dtype=torch.bfloat16) * 1.6)(D, 3 * D)),
            "wo": _w((lambda *s: torch.randn(*s, dtype=torch.bfloat16) * 0.05)(D, D)),
        }
    _B_in = _B_setup()

    return {
        "A_x": _A_in["x"],
        "A_wqkv": _A_in["wqkv"],
        "A_wo": _A_in["wo"],
        "B_x": _B_in["x"],
        "B_wqkv": _B_in["wqkv"],
        "B_wo": _B_in["wo"],
        "gate_w": _w((lambda *s: torch.randn(*s, dtype=torch.bfloat16) * 0.05)(512) * 16.0),
    }

def reference(A_x, A_wqkv, A_wo, B_x, B_wqkv, B_wo, gate_w):
    def _A_ref(x, wqkv, wo):
        B, S, D = x.shape
        H = 32; Dh = D // H
        qkv = (lambda x, *d: x.permute(*d))((x @ wqkv).reshape(B, S, 3, H, Dh), 2, 0, 3, 1, 4)
        q, k, v = qkv[0], qkv[1], qkv[2]
        phi = lambda t: torch.where(t > 0, t + 1, torch.exp(t)) + 1e-6
        pq, pk = phi(q), phi(k)
        kv = torch.einsum("bhsd,bhse->bhde", pk, v)
        z = torch.einsum("bhsd->bhd", pk)
        num = torch.einsum("bhqd,bhde->bhqe", pq, kv)
        den = torch.einsum("bhqd,bhd->bhq", pq, z)[..., None] + 1e-6
        o = num / den
        return (lambda x, *d: x.permute(*d))(o, 0, 2, 1, 3).reshape(B, S, D) @ wo

    def _B_ref(x, wqkv, wo):
        B, S, D = x.shape
        H = 32; Dh = D // H; W = 256
        qkv = (lambda x, *d: x.permute(*d))((x @ wqkv).reshape(B, S, 3, H, Dh), 2, 0, 3, 1, 4)
        q, k, v = qkv[0], qkv[1], qkv[2]
        scores = torch.einsum("bhqd,bhkd->bhqk", q, k) * (Dh ** -0.5)
        idx = torch.arange(S)
        mask = (idx[:, None] - idx[None, :] >= 0) & (idx[:, None] - idx[None, :] < W)
        scores = torch.where(mask[None, None], scores, -1e9)
        p = _softmax(scores, axis=-1)
        o = torch.einsum("bhqk,bhkd->bhqd", p, v)
        return (lambda x, *d: x.permute(*d))(o, 0, 2, 1, 3).reshape(B, S, D) @ wo

    x = A_x
    g = _sigmoid((x * gate_w).sum(-1, keepdims=True))
    a = _A_ref(x, A_wqkv, A_wo)
    b = _B_ref(x, B_wqkv, B_wo)
    return g * a + (1 - g) * b
```

```cpp
#include <cuda_runtime.h>
#include <cuda.h>
#include <cuda_bf16.h>
#include <stdint.h>

#define GPEND 3
#define TREG 144
#define GREG 192
#define HREG 32
#define APFG 2
#define CHKG 64
#define QPFG 3
#define XGATE(n) (n)

namespace {

constexpr int SEQ = 2048, DM = 512;
constexpr float LOG2E = 1.4426950408889634f;
constexpr float QSCALE = 0.25f * LOG2E;

constexpr uint32_t OFF_X = 0;
constexpr uint32_t OFF_Z = 196608;
constexpr uint32_t OFF_WR = 198656;
constexpr uint32_t OFF_BAR = 231424;
constexpr uint32_t OFF_GTAB = OFF_BAR + 448;
constexpr uint32_t OFF_EPOCH = OFF_GTAB + 512;
constexpr uint32_t SMEM_BYTES = 232448;

enum : uint32_t {
  B_XFULL = 0, B_KVFULL = 8, B_KVEMPTY = 12, B_WFULL = 16, B_WEMPTY = 20, B_GATE = 24, B_KV1ST = 25, B_HRETRY = 26,
  B_QREAD = 27, B_HFULL = 28, B_HEMPTY = 30, B_TDONE = 32, B_OBFULL = 33, B_OBEMPTY = 41, B_EPOCH = 45, B_OPUB = 46,
  B_EFREE = 49, B_VALX = 50, B_KVST = 52, B_WRFREE = 53, B_HVALID = 55, B_COUNT = 56,
  B_GREADY = B_GATE, B_GPUB = B_EPOCH
};

constexpr uint64_t TAB_K0 = 0x09141F1B120C1816ull, TAB_K1 = 0x07131D19110B1715ull, TAB_VS = 0x0504100F03010E0Dull;
__host__ __device__ constexpr uint32_t tab(uint64_t t, uint32_t i) { return (uint32_t)(t >> (8 * i)) & 255u; }
__host__ __device__ constexpr uint32_t unit_off(uint32_t pos) { return OFF_Z - pos * 2048; }
__host__ __device__ constexpr uint32_t ob_of(uint32_t n) { return n < 8 ? (n & 3) : (n < 10 ? n - 2 : (n < 12 ? n - 6 : n - 12)); }
__host__ __device__ constexpr bool is_b(uint32_t n) { return n < 6 || n >= 14; }
__host__ __device__ constexpr uint32_t valid_bar(uint32_t ob) { return ob < 4 ? B_KVFULL + ob : (ob < 6 ? B_HFULL + ob - 4 : B_VALX + ob - 6); }
__host__ __device__ constexpr uint32_t b_head(uint32_t n) { return n < 6 ? n >> 1 : 3; }
__host__ __device__ constexpr uint32_t a_grp(uint32_t n) { return n - 6; }
__host__ __device__ constexpr uint32_t ob_off(uint32_t ob, uint32_t half) {
  return ob < 2 ? OFF_WR + ob * 16384 + half * 8192
       : unit_off(ob == 2 ? 32 - 4 * half : (ob == 3 ? 24 - 8 * half : (ob == 4 ? 8 - 4 * half : 12 + 8 * half)));
}

__host__ __device__ constexpr uint32_t tile_off(uint32_t ob, uint32_t k) { return ob < 6 ? ob_off(ob, k >> 1) + (k & 1) * 4096 : OFF_X + ((ob - 6) * 4 + k) * 8192; }

struct Scratch {
  uint8_t kvg[16 * 8 * 4 * 8192];
  uint8_t ob[16 * 4 * 8 * 4096];
  uint8_t oa[16 * 8 * 4 * 4096];
  float4 kva[2][32][3][32];
  uint32_t kvf[16 * 8 * 4 * 8];
  uint32_t obf[16 * 4 * 2 * 8];
  uint32_t oaf[16 * 8];
  uint4 q23[128 * 2 * 256];
  uint32_t gf[16 * 8];
  float gate[2048];
  uint32_t epoch[8];
};
__device__ __align__(1024) Scratch g_scr;

#define TLPARAM
#define TLPASS
#define TLARG
#define TLARG0
#define TS(i)
#define TR(v)
#define TSX(i)
#define TW(i, v)
#define TL(i)
#define TLW(i)

constexpr uint32_t SPIN_LIMIT = 1u << 17;

__device__ __forceinline__ uint32_t d16(uint32_t addr) { return (addr & 0x3FFFFu) >> 4; }
__device__ __forceinline__ int tid_x() { int v; asm volatile("mov.u32 %0, %tid.x;" : "=r"(v)); return v; }
__device__ __forceinline__ void mbar_init(uint32_t bar, uint32_t cnt) { asm volatile("mbarrier.init.shared::cta.b64 [%0], %1;" :: "r"(bar), "r"(cnt) : "memory"); }
__device__ __forceinline__ void mbar_expect(uint32_t bar, uint32_t bytes) { asm volatile("mbarrier.arrive.expect_tx.shared::cta.b64 _, [%0], %1;" :: "r"(bar), "r"(bytes) : "memory"); }
__device__ __forceinline__ void mbar_arrive(uint32_t bar) { asm volatile("mbarrier.arrive.shared::cta.b64 _, [%0];" :: "r"(bar) : "memory"); }
__device__ __forceinline__ uint32_t map_cta(uint32_t addr, uint32_t cta) { uint32_t r; asm("mapa.shared::cluster.u32 %0, %1, %2;" : "=r"(r) : "r"(addr), "r"(cta)); return r; }
__device__ __forceinline__ void mbar_arrive_remote(uint32_t rbar) { asm volatile("mbarrier.arrive.shared::cluster.b64 _, [%0];" :: "r"(rbar) : "memory"); }
__device__ __forceinline__ void mbar_wait(uint32_t bar, uint32_t parity) {
  asm volatile("{\n.reg .pred p, q;\n.reg .u32 n;\nmov.u32 n, 0;\n"
    "LW:\nmbarrier.try_wait.parity.shared::cta.b64 p, [%0], %1;\nadd.u32 n, n, 1;\n"
    "setp.lt.and.u32 q, n, %2, !p;\n@q bra LW;\n}" :: "r"(bar), "r"(parity), "n"(SPIN_LIMIT) : "memory");
}
__device__ __forceinline__ uint32_t ld_relaxed(const uint32_t* p) { uint32_t v; asm volatile("ld.relaxed.gpu.global.u32 %0, [%1];" : "=r"(v) : "l"(p) : "memory"); return v; }
__device__ __forceinline__ void poll_ge(const uint32_t* p, uint32_t target) {
  uint32_t n = 0;
  while ((int32_t)(ld_relaxed(p) - target) < 0 && ++n < SPIN_LIMIT) {}
}
__device__ __forceinline__ void red_release(uint32_t* p, uint32_t v) { asm volatile("red.release.gpu.global.add.u32 [%0], %1;" :: "l"(p), "r"(v) : "memory"); }
__device__ __forceinline__ void red_relaxed(uint32_t* p, uint32_t v) { asm volatile("red.relaxed.gpu.global.add.u32 [%0], %1;" :: "l"(p), "r"(v) : "memory"); }
__device__ __forceinline__ void fence_async_smem() { asm volatile("fence.proxy.async.shared::cta;" ::: "memory"); }
__device__ __forceinline__ void named_sync(int id, int n) { asm volatile("bar.sync %0, %1;" :: "r"(id), "r"(n) : "memory"); }

__device__ __forceinline__ void tma2d(uint32_t dst, const CUtensorMap* tm, int c0, int c1, uint32_t bar) {
  asm volatile("cp.async.bulk.tensor.2d.shared::cluster.global.mbarrier::complete_tx::bytes [%0], [%1, {%3, %4}], [%2];"
    :: "r"(dst), "l"(tm), "r"(bar), "r"(c0), "r"(c1) : "memory");
}
__device__ __forceinline__ void tma2d_mc(uint32_t dst, const CUtensorMap* tm, int c0, int c1, uint32_t bar) {
  asm volatile("cp.async.bulk.tensor.2d.shared::cluster.global.mbarrier::complete_tx::bytes.multicast::cluster [%0], [%1, {%3, %4}], [%2], %5;"
    :: "r"(dst), "l"(tm), "r"(bar), "r"(c0), "r"(c1), "h"((uint16_t)3) : "memory");
}
__device__ __forceinline__ void tma3d(uint32_t dst, const CUtensorMap* tm, int c0, int c1, uint32_t bar) {
  asm volatile("cp.async.bulk.tensor.3d.shared::cluster.global.mbarrier::complete_tx::bytes [%0], [%1, {%3, %4, 0}], [%2];"
    :: "r"(dst), "l"(tm), "r"(bar), "r"(c0), "r"(c1) : "memory");
}
__device__ __forceinline__ void tma3d_mc(uint32_t dst, const CUtensorMap* tm, int c0, int c1, uint32_t bar) {
  asm volatile("cp.async.bulk.tensor.3d.shared::cluster.global.mbarrier::complete_tx::bytes.multicast::cluster [%0], [%1, {%3, %4, 0}], [%2], %5;"
    :: "r"(dst), "l"(tm), "r"(bar), "r"(c0), "r"(c1), "h"((uint16_t)3) : "memory");
}
__device__ __forceinline__ void tma3d_prefetch(const CUtensorMap* tm, int c0, int c1) {
  asm volatile("cp.async.bulk.prefetch.tensor.3d.L2.global [%0, {%1, %2, 0}];" :: "l"(tm), "r"(c0), "r"(c1) : "memory");
}
__device__ __forceinline__ void prefetch_l2(const void* p) { asm volatile("prefetch.global.L2 [%0];" :: "l"(p)); }
__device__ __forceinline__ void tma2d_store(const CUtensorMap* tm, int c0, int c1, uint32_t src) {
  asm volatile("cp.async.bulk.tensor.2d.global.shared::cta.bulk_group [%0, {%2, %3}], [%1];" :: "l"(tm), "r"(src), "r"(c0), "r"(c1) : "memory");
}
__device__ __forceinline__ void bulk_g2s(uint32_t dst, const void* src, uint32_t bytes, uint32_t bar) {
  asm volatile("cp.async.bulk.shared::cluster.global.mbarrier::complete_tx::bytes [%0], [%1], %2, [%3];" :: "r"(dst), "l"(src), "r"(bytes), "r"(bar) : "memory");
}

__device__ __forceinline__ void wg_fence() { asm volatile("wgmma.fence.sync.aligned;" ::: "memory"); }
__device__ __forceinline__ void wg_commit() { asm volatile("wgmma.commit_group.sync.aligned;" ::: "memory"); }
template <int N> __device__ __forceinline__ void wg_wait() { asm volatile("wgmma.wait_group.sync.aligned %0;" :: "n"(N) : "memory"); }

#define F4(d, o) "+f"(d[o]), "+f"(d[o + 1]), "+f"(d[o + 2]), "+f"(d[o + 3])
#define F16(d, o) F4(d, o), F4(d, o + 4), F4(d, o + 8), F4(d, o + 12)
#define W4(d, o) "=f"(d[o]), "=f"(d[o + 1]), "=f"(d[o + 2]), "=f"(d[o + 3])
#define W16(d, o) W4(d, o), W4(d, o + 4), W4(d, o + 8), W4(d, o + 12)
#define R64 "{%0,%1,%2,%3,%4,%5,%6,%7,%8,%9,%10,%11,%12,%13,%14,%15,%16,%17,%18,%19,%20,%21,%22,%23,%24,%25,%26,%27,%28,%29,%30,%31," \
            "%32,%33,%34,%35,%36,%37,%38,%39,%40,%41,%42,%43,%44,%45,%46,%47,%48,%49,%50,%51,%52,%53,%54,%55,%56,%57,%58,%59,%60,%61,%62,%63}"

template <int TA, int TB, uint32_t HIA, uint32_t HIB, bool FRESH = false>
__device__ __forceinline__ void mma128(float (&d)[64], uint32_t la, uint32_t oa, uint32_t lb, uint32_t ob) {
#define MMA128_ASM(SC) "{\n.reg .b32 x, y;\n.reg .b64 da, db;\nadd.u32 x, %64, %65;\nadd.u32 y, %66, %67;\nmov.b64 da, {x, %70};\nmov.b64 db, {y, %71};\n" \
    "wgmma.mma_async.sync.aligned.m64n128k16.f32.bf16.bf16 " R64 ", da, db, " SC ", 1, 1, %68, %69;\n}"
  if (FRESH) asm volatile(MMA128_ASM("0") : W16(d, 0), W16(d, 16), W16(d, 32), W16(d, 48) : "r"(la), "r"(oa), "r"(lb), "r"(ob), "n"(TA), "n"(TB), "r"(HIA), "r"(HIB));
  else asm volatile(MMA128_ASM("1") : F16(d, 0), F16(d, 16), F16(d, 32), F16(d, 48) : "r"(la), "r"(oa), "r"(lb), "r"(ob), "n"(TA), "n"(TB), "r"(HIA), "r"(HIB));
}
template <bool FRESH = false> __device__ __forceinline__ void mma96(float (&d)[48], uint32_t la, uint32_t oa, uint32_t lb, uint32_t ob) {
#define MMA96_ASM(SC) "{\n.reg .b32 x, y;\n.reg .b64 da, db;\nadd.u32 x, %48, %49;\nadd.u32 y, %50, %51;\nmov.b64 da, {x, %52};\nmov.b64 db, {y, %53};\n" \
    "wgmma.mma_async.sync.aligned.m64n96k16.f32.bf16.bf16 " \
    "{%0,%1,%2,%3,%4,%5,%6,%7,%8,%9,%10,%11,%12,%13,%14,%15,%16,%17,%18,%19,%20,%21,%22,%23,%24,%25,%26,%27,%28,%29,%30,%31," \
    "%32,%33,%34,%35,%36,%37,%38,%39,%40,%41,%42,%43,%44,%45,%46,%47}, da, db, " SC ", 1, 1, 0, 1;\n}"
  if (FRESH) asm volatile(MMA96_ASM("0") : W16(d, 0), W16(d, 16), W16(d, 32) : "r"(la), "r"(oa), "r"(lb), "r"(ob), "r"(0x40000040u), "r"(0x80000020u));
  else asm volatile(MMA96_ASM("1") : F16(d, 0), F16(d, 16), F16(d, 32) : "r"(la), "r"(oa), "r"(lb), "r"(ob), "r"(0x40000040u), "r"(0x80000020u));
}
constexpr uint32_t HI_SW128 = 0x40000040u, HI_PLANE = 8u;
#define MMA_W(first, acc, la, oa, lb, ob) do { if (first) mma128<1, 0, HI_SW128, HI_SW128, true>(acc, la, oa, lb, ob); else mma128<1, 0, HI_SW128, HI_SW128>(acc, la, oa, lb, ob); } while (0)
template <int N> __device__ __forceinline__ void zero_acc(float (&d)[N]) {
#pragma unroll
  for (int i = 0; i < N; i++) asm volatile("mov.f32 %0, 0f00000000;" : "=f"(d[i]));
}
__device__ __forceinline__ void qk64(float (&d)[32], const uint32_t (&a)[4], uint64_t db) {
  asm volatile("wgmma.mma_async.sync.aligned.m64n64k16.f32.bf16.bf16 "
    "{%0,%1,%2,%3,%4,%5,%6,%7,%8,%9,%10,%11,%12,%13,%14,%15,%16,%17,%18,%19,%20,%21,%22,%23,%24,%25,%26,%27,%28,%29,%30,%31}, {%32,%33,%34,%35}, %36, 0, 1, 1, 0;"
    : W16(d, 0), W16(d, 16) : "r"(a[0]), "r"(a[1]), "r"(a[2]), "r"(a[3]), "l"(db));
}
template <int O> __device__ __forceinline__ void qk32(float (&d)[32], const uint32_t (&a)[4], uint64_t db) {
  asm volatile("wgmma.mma_async.sync.aligned.m64n32k16.f32.bf16.bf16 "
    "{%0,%1,%2,%3,%4,%5,%6,%7,%8,%9,%10,%11,%12,%13,%14,%15}, {%16,%17,%18,%19}, %20, 0, 1, 1, 0;"
    : W16(d, O) : "r"(a[0]), "r"(a[1]), "r"(a[2]), "r"(a[3]), "l"(db));
}
template <int O, int ACC> __device__ __forceinline__ void pv24(float (&d)[12], const uint32_t (&p)[16], uint64_t db) {
  asm volatile("wgmma.mma_async.sync.aligned.m64n24k16.f32.bf16.bf16 "
    "{%0,%1,%2,%3,%4,%5,%6,%7,%8,%9,%10,%11}, {%12,%13,%14,%15}, %16, %17, 1, 1, 1;"
    : F4(d, 0), F4(d, 4), F4(d, 8) : "r"(p[O]), "r"(p[O + 1]), "r"(p[O + 2]), "r"(p[O + 3]), "l"(db), "n"(ACC));
}
__device__ __forceinline__ void hmma(float (&d)[4], uint32_t a0, uint32_t a1, uint32_t a2, uint32_t a3, uint32_t b0, uint32_t b1) {
  asm volatile("mma.sync.aligned.m16n8k16.row.col.f32.bf16.bf16.f32 {%0,%1,%2,%3}, {%4,%5,%6,%7}, {%8,%9}, {%0,%1,%2,%3};"
    : "+f"(d[0]), "+f"(d[1]), "+f"(d[2]), "+f"(d[3]) : "r"(a0), "r"(a1), "r"(a2), "r"(a3), "r"(b0), "r"(b1));
}
__device__ __forceinline__ void stsm4(uint32_t addr, uint32_t r0, uint32_t r1, uint32_t r2, uint32_t r3) {
  asm volatile("stmatrix.sync.aligned.m8n8.x4.shared.b16 [%0], {%1,%2,%3,%4};" :: "r"(addr), "r"(r0), "r"(r1), "r"(r2), "r"(r3) : "memory");
}
__device__ __forceinline__ void stsm4t(uint32_t addr, uint32_t r0, uint32_t r1, uint32_t r2, uint32_t r3) {
  asm volatile("stmatrix.sync.aligned.m8n8.x4.trans.shared.b16 [%0], {%1,%2,%3,%4};" :: "r"(addr), "r"(r0), "r"(r1), "r"(r2), "r"(r3) : "memory");
}
__device__ __forceinline__ uint32_t movm(uint32_t a) { uint32_t d; asm volatile("movmatrix.sync.aligned.m8n8.trans.b16 %0, %1;" : "=r"(d) : "r"(a)); return d; }
__device__ __forceinline__ float ex2(float x) { float y; asm volatile("ex2.approx.ftz.f32 %0, %1;" : "=f"(y) : "f"(x)); return y; }
__device__ __forceinline__ float rcp(float x) { float y; asm("rcp.approx.ftz.f32 %0, %1;" : "=f"(y) : "f"(x)); return y; }
__device__ __forceinline__ uint32_t pack2(float lo, float hi) { uint32_t r; asm("cvt.rn.bf16x2.f32 %0, %1, %2;" : "=r"(r) : "f"(hi), "f"(lo)); return r; }
__device__ __forceinline__ float lds_f32(uint32_t addr) { float v; asm volatile("ld.shared.f32 %0, [%1];" : "=f"(v) : "r"(addr) : "memory"); return v; }
__device__ __forceinline__ uint32_t lds_u32(uint32_t addr) { uint32_t v; asm volatile("ld.shared.u32 %0, [%1];" : "=r"(v) : "r"(addr) : "memory"); return v; }
__device__ __forceinline__ void stg32(void* p, uint32_t v) { asm volatile("st.global.u32 [%0], %1;" :: "l"(p), "r"(v) : "memory"); }
__device__ __forceinline__ uint4 lds128(uint32_t addr) { uint4 v; asm volatile("ld.shared.v4.u32 {%0,%1,%2,%3}, [%4];" : "=r"(v.x), "=r"(v.y), "=r"(v.z), "=r"(v.w) : "r"(addr) : "memory"); return v; }
__device__ __forceinline__ float dot2(uint32_t a, uint32_t b, float s) {
  s = fmaf(__uint_as_float(a << 16), __uint_as_float(b << 16), s);
  return fmaf(__uint_as_float(a & 0xffff0000u), __uint_as_float(b & 0xffff0000u), s);
}
__device__ __forceinline__ float dot8(uint4 a, uint4 b, float s) { return dot2(a.w, b.w, dot2(a.z, b.z, dot2(a.y, b.y, dot2(a.x, b.x, s)))); }
__device__ __forceinline__ float phi(float t) { return __saturatef(ex2(t * LOG2E) + 1e-6f) + fmaxf(t, 0.f); }

template <int H, int HH, int N> __device__ __forceinline__ void st_kv(const float (&a)[N], uint32_t ra, bool hi) {
  stsm4(ra + (hi ? unit_off(tab(TAB_K1, 4 + H)) : unit_off(tab(TAB_K0, 4 + H))), pack2(a[16 + 8 * HH], a[17 + 8 * HH]), pack2(a[18 + 8 * HH], a[19 + 8 * HH]),
        pack2(a[20 + 8 * HH], a[21 + 8 * HH]), pack2(a[22 + 8 * HH], a[23 + 8 * HH]));
  stsm4(ra + (hi ? unit_off(tab(TAB_VS, 4 + H)) : unit_off(2 * tab(TAB_VS, 4 + H))), pack2(a[32 + 8 * HH], a[33 + 8 * HH]), pack2(a[34 + 8 * HH], a[35 + 8 * HH]),
        pack2(a[36 + 8 * HH], a[37 + 8 * HH]), pack2(a[38 + 8 * HH], a[39 + 8 * HH]));
}
template <int M0, int M1, int N> __device__ __forceinline__ void stg_kv(const float (&a)[N], uint8_t* gp, uint32_t tm = ~0u, uint32_t tb = 0u) {
#pragma unroll
  for (int m = M0; m < M1; m++) {
    stg32(gp + (m >> 2) * 8192 + ((m >> 1) & 1) * 2048 + (m & 1) * 128, (pack2(a[16 + 2 * m], a[17 + 2 * m]) & tm) | tb);
    stg32(gp + (m >> 2) * 8192 + 4096 + ((m >> 1) & 1) * 2048 + (m & 1) * 128, (pack2(a[32 + 2 * m], a[33 + 2 * m]) & tm) | tb);
  }
}

struct TCtx { bool p0, p1; uint32_t msk; };
__device__ __forceinline__ void exp_pack32(float (&s)[32], uint32_t (&p)[16]) {
#pragma unroll
  for (int i = 0; i < 16; i++) p[i] = pack2(ex2(s[2 * i]), ex2(s[2 * i + 1]));
}
template <int SO, int PO> __device__ __forceinline__ void merged_kstep(float (&s)[32], uint32_t (&p)[16], int rel, const TCtx& c) {
  if (rel > 0) {
#pragma unroll
    for (int i = 0; i < 4; i++) { p[PO + i] = pack2(ex2(s[SO + 2 * i]), ex2(s[SO + 2 * i + 1])); p[8 + PO + i] = 0u; }
  } else if (rel < 0) {
#pragma unroll
    for (int i = 0; i < 4; i++) { p[8 + PO + i] = pack2(ex2(s[16 + SO + 2 * i]), ex2(s[16 + SO + 2 * i + 1])); p[PO + i] = 0u; }
  } else {
    uint32_t x0 = pack2(ex2(c.p0 ? s[SO] : s[16 + SO]), ex2(c.p1 ? s[SO + 1] : s[16 + SO + 1]));
    uint32_t x1 = pack2(ex2(s[16 + SO + 2]), ex2(s[16 + SO + 3]));
    uint32_t x2 = pack2(ex2(s[SO + 4]), ex2(s[SO + 5]));
    uint32_t x3 = pack2(ex2(c.p0 ? s[SO + 6] : s[16 + SO + 6]), ex2(c.p1 ? s[SO + 7] : s[16 + SO + 7]));
    p[PO] = x0 & c.msk; p[PO + 1] = 0u; p[PO + 2] = x2; p[PO + 3] = x3 & c.msk;
    p[8 + PO] = x0 & ~c.msk; p[8 + PO + 1] = x1; p[8 + PO + 2] = 0u; p[8 + PO + 3] = x3 & ~c.msk;
  }
}

__device__ __forceinline__ bool normalize_head(const float (&o)[12], float g0, float g1, uint4& v) {
  const float l0 = o[8], l1 = o[10];
  const float m = fmaxf(fmaxf(fmaxf(fabsf(o[0]), fabsf(o[1])), fmaxf(fabsf(o[2]), fabsf(o[3]))), fmaxf(fmaxf(fabsf(o[4]), fabsf(o[5])), fmaxf(fabsf(o[6]), fabsf(o[7]))));
  const float r0 = g0 * rcp(l0), r1 = g1 * rcp(l1);
  v = make_uint4(pack2(o[0] * r0, o[1] * r0), pack2(o[2] * r1, o[3] * r1), pack2(o[4] * r0, o[5] * r0), pack2(o[6] * r1, o[7] * r1));
  return __all_sync(0xffffffffu, (l0 >= 0x1p-60f) && (l0 <= 0x1p100f) && (l1 >= 0x1p-60f) && (l1 <= 0x1p100f) && (m <= 0x1p126f));
}
__device__ __forceinline__ void store_head(bool st, const uint4& v, uint8_t* dst, uint32_t pubbar, bool pub = true) {
  asm volatile("{\n.reg .pred p, q;\nsetp.ne.u32 p, %5, 0;\nsetp.ne.u32 q, %6, 0;\n"
    "@p st.global.u32 [%0], %1;\n@p st.global.u32 [%0+128], %2;\n@p st.global.u32 [%0+2048], %3;\n@p st.global.u32 [%0+2176], %4;\n"
    "bar.warp.sync 0xffffffff;\n@q mbarrier.arrive.shared::cta.b64 _, [%7];\n}"
    :: "l"(dst), "r"(v.x), "r"(v.y), "r"(v.z), "r"(v.w), "r"((uint32_t)st), "r"((uint32_t)(st && pub && (threadIdx.x & 31) == 0)), "r"(pubbar) : "memory");
}

__device__ __forceinline__ uint4 slow_head(const Scratch* scr, uint4 qv, int r, int c, int h, int row0, float g0, float g1) {
  const int lane = threadIdx.x & 31, g = lane >> 2, t = lane & 3;
  const int q0 = r * 128 + row0;
  float m0 = -INFINITY, m1 = -INFINITY, l0 = 0.f, l1 = 0.f;
  float o0[4] = {0.f, 0.f, 0.f, 0.f}, o1[4] = {0.f, 0.f, 0.f, 0.f};
#pragma unroll 1
  for (int pass = 0; pass < 2; pass++) {
#pragma unroll 1
    for (int b = 0; b <= 16; b++) {
      const int k0 = q0 - 256 + 16 * b;
      if (k0 < 0) continue;
      const uint8_t* kv = scr->kvg + (size_t)(((k0 >> 7) * 8 + c) * 4 + h) * 8192 + (k0 & 127) * 16;
      float s[2][4];
#pragma unroll
      for (int n = 0; n < 2; n++) {
        uint32_t b0 = ld_relaxed((const uint32_t*)(kv + (8 * n + g) * 16 + t * 4));
        uint32_t b1 = ld_relaxed((const uint32_t*)(kv + 2048 + (8 * n + g) * 16 + t * 4));
        s[n][0] = s[n][1] = s[n][2] = s[n][3] = 0.f;
        hmma(s[n], qv.x, qv.y, qv.z, qv.w, b0, b1);
#pragma unroll
        for (int e = 0; e < 4; e++) {
          int d = (q0 + g + 8 * (e >> 1)) - (k0 + 8 * n + 2 * t + (e & 1));
          if (d < 0 || d >= 256) s[n][e] = -INFINITY;
        }
      }
      if (pass == 0) {
        m0 = fmaxf(m0, fmaxf(fmaxf(s[0][0], s[0][1]), fmaxf(s[1][0], s[1][1])));
        m1 = fmaxf(m1, fmaxf(fmaxf(s[0][2], s[0][3]), fmaxf(s[1][2], s[1][3])));
      } else {
        uint32_t p[4];
#pragma unroll
        for (int n = 0; n < 2; n++) {
          p[2 * n] = pack2(ex2(s[n][0] - m0), ex2(s[n][1] - m0));
          p[2 * n + 1] = pack2(ex2(s[n][2] - m1), ex2(s[n][3] - m1));
          l0 += __uint_as_float(p[2 * n] << 16) + __uint_as_float(p[2 * n] & 0xffff0000u);
          l1 += __uint_as_float(p[2 * n + 1] << 16) + __uint_as_float(p[2 * n + 1] & 0xffff0000u);
        }
#pragma unroll
        for (int n = 0; n < 2; n++) {
          const uint8_t* v = kv + 4096 + n * 2048 + (g >> 1) * 4;
          const uint32_t sel = (g & 1) ? 0x7632u : 0x5410u;
          uint32_t b0 = __byte_perm(ld_relaxed((const uint32_t*)(v + (2 * t) * 16)), ld_relaxed((const uint32_t*)(v + (2 * t + 1) * 16)), sel);
          uint32_t b1 = __byte_perm(ld_relaxed((const uint32_t*)(v + (2 * t + 8) * 16)), ld_relaxed((const uint32_t*)(v + (2 * t + 9) * 16)), sel);
          if (n == 0) hmma(o0, p[0], p[1], p[2], p[3], b0, b1); else hmma(o1, p[0], p[1], p[2], p[3], b0, b1);
        }
      }
    }
    if (pass == 0) {
      m0 = fmaxf(m0, __shfl_xor_sync(0xffffffffu, m0, 1)); m0 = fmaxf(m0, __shfl_xor_sync(0xffffffffu, m0, 2));
      m1 = fmaxf(m1, __shfl_xor_sync(0xffffffffu, m1, 1)); m1 = fmaxf(m1, __shfl_xor_sync(0xffffffffu, m1, 2));
    }
  }
  l0 += __shfl_xor_sync(0xffffffffu, l0, 1); l0 += __shfl_xor_sync(0xffffffffu, l0, 2);
  l1 += __shfl_xor_sync(0xffffffffu, l1, 1); l1 += __shfl_xor_sync(0xffffffffu, l1, 2);
  const float r0 = g0 * rcp(l0), r1 = g1 * rcp(l1);
  return make_uint4(pack2(o0[0] * r0, o0[1] * r0), pack2(o0[2] * r1, o0[3] * r1), pack2(o1[0] * r0, o1[1] * r0), pack2(o1[2] * r1, o1[3] * r1));
}

#define PV4(O, P, ACC0, d0, d1) do { const uint64_t d0_ = d0, d1_ = d1; wg_fence(); pv24<0, ACC0>(O, P, d0_); pv24<4, 1>(O, P, d0_ + 16); pv24<8, 1>(O, P, d1_); pv24<12, 1>(O, P, d1_ + 16); wg_commit(); } while (0)

__device__ __forceinline__ uint64_t kdesc(uint32_t a0, uint32_t a1, uint32_t i) {
  uint64_t d;
  asm volatile("{\n.reg .u32 lo, t;\nsub.u32 t, %2, %1;\nmad.lo.u32 lo, t, %3, %1;\nmov.b64 %0, {lo, %4};\n}" : "=l"(d) : "r"(a0), "r"(a1), "r"(i), "r"(8u));
  return d;
}
__device__ __forceinline__ uint64_t vdesc(uint32_t s0, uint32_t s1, uint32_t i, uint32_t base, uint32_t present) {
  uint64_t d;
  asm volatile("{\n.reg .u32 lo, hi, t;\nsub.u32 t, %2, %1;\nmad.lo.u32 hi, t, %3, %1;\nmad.lo.u32 lo, hi, 0xFFFFFFFE, %4;\nand.b32 hi, hi, %5;\nmov.b64 %0, {lo, hi};\n}"
    : "=l"(d) : "r"(s0), "r"(s1), "r"(i), "r"(base), "r"(present));
  return d;
}

struct GCtx { uint32_t bar, abar; bool sig, arm, osig; };
template <int PEND, class Hook>
__device__ __forceinline__ void g_pass(float (&acc)[64], uint32_t sb, const GCtx& g, Hook hook) {
  const uint32_t dx = (1u << 16) + d16(sb + OFF_X), dw = (1u << 16) + d16(sb + OFF_WR);
  mbar_wait(g.bar + 8 * B_WFULL, 0);
  wg_fence();
#pragma unroll
  for (int i = 0; i < 8; i++) {
#pragma unroll
    for (int k = 0; k < 4; k++) {
      if (i | k) wg_wait<PEND>();
      MMA_W((i | k) == 0, acc, dw, (i & 3) * 512 + k * 128, dx, i * 1024 + k * 2); wg_commit();
      if (k == PEND && i > 0) {
        if (g.arm) mbar_expect(g.bar + 8 * (B_WFULL + ((i - 1) & 3)), 8192);
        if (g.sig) mbar_arrive_remote(g.abar + 8 * (B_WEMPTY + ((i - 1) & 3)));
      }
      hook(i, k);
      if (k == 3 && i < 7) mbar_wait(g.bar + 8 * (B_WFULL + ((i + 1) & 3)), ((i + 1) >> 2) & 1);
    }
  }
  wg_wait<0>();
  if (g.arm) mbar_expect(g.bar + 8 * (B_WFULL + 3), 8192);
  if (g.sig) mbar_arrive_remote(g.abar + 8 * (B_WEMPTY + 3));
}

template <int PEND>
__device__ __forceinline__ void g_pass_last(float (&acc)[64], uint32_t sb, const GCtx& g) {
  constexpr bool last = true;
  uint32_t dx = (1u << 16) + d16(sb + OFF_X);
  const uint32_t dw = (1u << 16) + d16(sb + OFF_WR);
  zero_acc(acc);
  mbar_wait(g.bar + 8 * B_WFULL, 0);
  wg_fence();
#pragma unroll 1
  for (uint32_t rd = 0; rd < 2; rd++) {
    const bool arm = g.arm && !(last && rd);
#pragma unroll
    for (int i = 0; i < 4; i++) {
#pragma unroll
      for (int k = 0; k < 4; k++) {
        wg_wait<PEND>();
        MMA_W(false, acc, dw, i * 512 + k * 128, dx, i * 1024 + k * 2); wg_commit();
        if (k == PEND) {
          if (i == 0 ? (g.arm && rd) : arm) mbar_expect(g.bar + 8 * (B_WFULL + ((i + 3) & 3)), 8192);
          if (g.sig && (i > 0 || rd)) mbar_arrive_remote(g.abar + 8 * (B_WEMPTY + ((i + 3) & 3)));
          if (i == 2 && g.osig && last && rd) mbar_arrive(g.bar + 8 * B_WRFREE);
        }
      }
      if (i < 3) mbar_wait(g.bar + 8 * (B_WFULL + i + 1), rd);
      else if (!rd) mbar_wait(g.bar + 8 * B_WFULL, 1);
    }
    dx += 4096;
  }
  wg_wait<0>();
  if (g.arm && !last) mbar_expect(g.bar + 8 * (B_WFULL + 3), 8192);
  if (g.sig) mbar_arrive_remote(g.abar + 8 * (B_WEMPTY + 3));
  if (last && g.osig) mbar_arrive(g.bar + 8 * (B_WRFREE + 1));
}

template <uint32_t n, int HALF> __device__ __forceinline__ void out_mma(float (&acc)[64], uint32_t dwo, uint32_t dob) {
  constexpr uint32_t wstep = is_b(n) ? 512 : 128, wofs = (is_b(n) ? (n & 1) * 2048 + b_head(n) * 128 : 4096 + a_grp(n) * 512) + 2 * HALF * wstep;
  constexpr uint32_t db = tile_off(ob_of(n), 2 * HALF) >> 4, db1 = tile_off(ob_of(n), 2 * HALF + 1) >> 4;
  mma128<1, 0, HI_SW128, HI_PLANE, n == 0 && HALF == 0>(acc, dwo, wofs, dob, db); mma128<1, 0, HI_SW128, HI_PLANE>(acc, dwo, wofs + wstep, dob, db1);
  wg_commit();
}
template <uint32_t n> __device__ __forceinline__ void out_steps(float (&acc)[64], uint32_t dwo, uint32_t dob, uint32_t bar, const GCtx& gc TLPARAM) {
  constexpr uint32_t m = n + 1;
  wg_fence();
  out_mma<n, 0>(acc, dwo, dob);
  if (n > 0 && n <= 8 && n != 4 && n != 6) {
    wg_wait<1>();
    if (gc.osig) mbar_arrive(bar + 8 * (B_OBEMPTY + ob_of(n - 1)));
  }
  out_mma<n, 1>(acc, dwo, dob);
  if (n == 3 || n == 5) {
    wg_wait<0>();
    if (gc.osig) mbar_arrive(bar + 8 * (B_OBEMPTY + ob_of(n)));
    if (gc.arm) mbar_arrive(bar + 8 * (n == 3 ? B_KVST : B_KV1ST));
  }
  if (m == 1) { mbar_wait(bar + 8 * (B_XFULL + 2), 1); mbar_wait(bar + 8 * (B_XFULL + 3), 1); }
  if (m < 16 && !is_b(m) && !(m & 1)) mbar_wait(bar + 8 * (B_XFULL + 4 + (a_grp(m) >> 1)), 1);
  if (m < 6) mbar_wait(bar + 8 * (B_OBFULL + ob_of(m)), m >= 4 ? 1 : 0);
  else if (m < 16) mbar_wait(bar + 8 * valid_bar(ob_of(m)), m >= 14 ? 1 : 0);
  if constexpr (m < 16) out_steps<m>(acc, dwo, dob, bar, gc TLPASS);
}

__device__ __forceinline__ void fetch_o(const Scratch* scr, uint32_t n, uint32_t sb, int ro, uint32_t epoch) {
  const uint32_t bar = sb + OFF_BAR, ob = ob_of(n);
  const bool isb = is_b(n);
  const uint32_t idx = isb ? (ro * 4 + b_head(n)) * 2 + (n & 1) : ro * 8 + a_grp(n);
  const uint8_t* src = (isb ? scr->ob : scr->oa) + (size_t)idx * 16384;
  const uint32_t fb = bar + 8 * (B_OBFULL + ob);
  if (isb || n < 10) poll_ge(isb ? scr->obf + idx * 8 : scr->oaf + ro * 8, (epoch + 1) * (n >= 6 ? 32 : 4));
  mbar_wait(bar + 8 * (n < 2 ? B_WRFREE + n : (n < 4 ? B_EFREE : (ob < 4 ? B_OBEMPTY + ob : (ob < 6 ? B_TDONE : B_KVST)))), (n >= 4 && n < 10) ? 1 : 0);
  TSX(64 + n);
  mbar_expect(fb, 16384);
  if (ob < 6) { bulk_g2s(sb + ob_off(ob, 0), src, 8192, fb); bulk_g2s(sb + ob_off(ob, 1), src + 8192, 8192, fb); }
  else {
#pragma unroll 1
    for (uint32_t k = 0; k < 4; k++) bulk_g2s(sb + tile_off(ob, k), src + k * 4096, 4096, fb);
  }
}

template <uint32_t LO, uint32_t HI> __device__ __forceinline__ void init_range(uint32_t bar) {
#pragma unroll
  for (uint32_t i = LO; i < HI; i++) {
    uint32_t cnt = 1;
    if ((i >= B_KVEMPTY && i < B_KVEMPTY + 4) || i == B_QREAD) cnt = 4;
    else if ((i >= B_WEMPTY && i < B_WEMPTY + 4) || (i >= B_HEMPTY && i < B_HEMPTY + 2) || i == B_EFREE || i == B_TDONE) cnt = 2;
    else if ((i >= B_OPUB && i < B_OPUB + 3)) cnt = 8;
    mbar_init(bar + 8 * i, cnt);
  }
}

__device__ __forceinline__ int logical_block() {
  const int q = blockIdx.x >> 1, t = q - 4, u = t - 32, d = (u * 37) >> 8;
  const int p = t < 0 ? 0 : (t < 32 ? (t & 7) : 1 + u - 7 * d), c = t < 0 ? 4 + q : (t < 32 ? (t >> 3) : 4 + d);
  return (p << 4) | (c << 1) | (blockIdx.x & 1);
}

__global__ void __cluster_dims__(2, 1, 1) __launch_bounds__(512, 1)
fused_kernel(Scratch* __restrict__ scr, const __nv_bfloat16* __restrict__ gate_w, const uint8_t* __restrict__ wa,
             const uint8_t* __restrict__ woa, const uint8_t* __restrict__ wob TLPARAM,
             const __grid_constant__ CUtensorMap tmX, const __grid_constant__ CUtensorMap tmWB, const __grid_constant__ CUtensorMap tmWA,
             const __grid_constant__ CUtensorMap tmOA, const __grid_constant__ CUtensorMap tmOB, const __grid_constant__ CUtensorMap tmOut) {
  extern __shared__ __align__(1024) uint8_t smem[];
  const uint32_t sb = (uint32_t)__cvta_generic_to_shared(smem);
  const uint32_t bar = sb + OFF_BAR;
  const int wg = __reduce_max_sync(0xffffffffu, threadIdx.x >> 7);
#define ROLE_IDS \
  const int warp = __reduce_max_sync(0xffffffffu, (unsigned)((tid_x() >> 5) & 3)); \
  const int lane = tid_x() & 31; \
  const int bid = logical_block(); \
  const int rank = bid & 1, c = (bid >> 1) & 7, r = ((bid >> 4) << 1) | rank; \
  const uint32_t peer = rank ^ 1; (void)peer; (void)warp; (void)lane; (void)r;

  TR(t_start);
  const int lb = logical_block();
  if ((threadIdx.x & 31) == 0) {
    const uint32_t w = threadIdx.x >> 5;
    if (w >= 8) {
      if (w < 12) { if (w == 8) init_range<0, 7>(bar); else if (w == 9) init_range<7, 14>(bar); else if (w == 10) init_range<14, 21>(bar); else init_range<21, 28>(bar); }
      else { if (w == 12) init_range<28, 35>(bar); else if (w == 13) init_range<35, 42>(bar); else if (w == 14) init_range<42, 49>(bar); else init_range<49, B_COUNT>(bar); }
    }
    else if (w == 0 && lb < 32) tma3d_prefetch(&tmWB, ((lb >> 1) & 7) * 64, (((lb >> 4) << 1) | (lb & 1)) * 64);
    else if (w == 1 && (lb & 12) == 0) asm volatile("cp.async.bulk.prefetch.tensor.2d.L2.global [%0, {%1, %2}];" :: "l"(&tmX), "r"((lb & 2) * 32), "r"((((lb >> 4) << 1) | (lb & 1)) * 128) : "memory");
  }
  asm volatile("fence.mbarrier_init.release.cluster;" ::: "memory");
  __syncwarp();
  asm volatile("barrier.cluster.arrive.relaxed.aligned;\nbarrier.cluster.wait.aligned;" ::: "memory");
  if (threadIdx.x == 256) {
#pragma unroll
    for (uint32_t w = 0; w < 2; w++) {
      mbar_expect(bar + 8 * (B_XFULL + w), 16384);
      tma2d(sb + OFF_X + w * 16384, &tmX, w * 64, (((lb >> 4) << 1) | (lb & 1)) * 128, bar + 8 * (B_XFULL + w));
    }
  } else if (threadIdx.x == 288) {
#pragma unroll
    for (uint32_t w = 0; w < 2; w++) mbar_expect(bar + 8 * (B_KVFULL + w), 12288);
    tma3d_mc(sb + OFF_Z - ((lb & 1) + 1) * 12288, &tmWB, ((lb >> 1) & 7) * 64, (lb & 1) * 64, bar + 8 * (B_KVFULL + (lb & 1)));
  }
  __syncwarp();

  if (wg < 2) {
    asm volatile("setmaxnreg.inc.sync.aligned.u32 %0;" :: "n"(TREG));
    ROLE_IDS
    const int wgi = __reduce_max_sync(0xffffffffu, (unsigned)(tid_x() >> 7));
    const int g = lane >> 2, t4 = lane & 3;
    const int row0 = wgi * 64 + warp * 16;
    uint32_t q[4], q1[4], q2[4], q3[4];
    const uint32_t ra = sb + (row0 + ((lane >> 3) & 1) * 8 + (lane & 7)) * 16;
    {
      float acc[48];
      zero_acc(acc);
      const uint32_t abar = map_cta(bar, warp == 0 ? rank : peer);
      const bool sig = lane == 0 && warp < 2;
      const uint32_t dx = (1u << 16) + d16(sb + OFF_X + wgi * 8192), dw = (256u << 16) + d16(sb + OFF_Z) - 768;
#pragma unroll 1
      for (uint32_t i = 0; i < 8; i++) {
        mbar_wait(bar + 8 * (B_XFULL + i), 0);
        mbar_wait(bar + 8 * (B_KVFULL + (i & 3)), i >> 2);
        wg_fence();
#pragma unroll
        for (int k = 0; k < 4; k++) mma96(acc, dx + i * 1024, k * 2, dw - (i & 3) * 768, k * 64);
        wg_commit();
        wg_wait<1>();
        if (i >= 1 && i < 7 && sig) mbar_arrive_remote(abar + 8 * (B_KVEMPTY + ((i - 1) & 3)));
      }
      mbar_wait(bar + 8 * B_EPOCH, 0);
      const uint32_t epoch = lds_u32(sb + OFF_EPOCH);
      wg_wait<0>();
      TR(t_kv);
      uint8_t* gp = scr->kvg + (size_t)(r * 8 + c) * 32768 + (row0 + g) * 16 + t4 * 4;
      stg_kv<0, 4>(acc, gp, t4 == 0 ? ~1u : ~0u, t4 == 0 ? (~epoch & 1u) : 0u);
      __syncwarp();
      if (lane == 0) red_relaxed(&scr->kvf[(r * 8 + c) * 32 + 16], 1);
      named_sync(1, 256);
      st_kv<0, 0>(acc, ra, lane >= 16); st_kv<1, 1>(acc, ra, lane >= 16);
      asm volatile("fence.proxy.async.shared::cta;" ::: "memory");
      stg_kv<4, 8>(acc, gp);
      named_sync(1, 256);
      if (threadIdx.x == 128) mbar_arrive(bar + 8 * B_KVST);
      TLW(3 + wgi); TW(1 + wgi, t_kv);
      if (wgi == 0) {
        const int blk = (~warp) & 1, rb = r - 2 + blk;
        const uint8_t* src = scr->kvg + (size_t)(rb * 8 + c) * 32768;
        const uint32_t ck = sb + threadIdx.x * 32 + ((threadIdx.x >> 2) & 1) * 16, cv = threadIdx.x < 64 ? ck + unit_off(26) : ck + unit_off(13) - 2048;
        if (lane == 0 && rb >= 0) poll_ge(&scr->kvf[(rb * 8 + c) * 32 + 16], (epoch + 1) * 8);
#pragma unroll 1
        for (uint32_t it = 0; it < SPIN_LIMIT; it++) {
          const uint32_t fb = bar + 8 * (it ? B_HRETRY : B_HFULL);
          if (lane == 0 && rb >= 0) {
            if (it && warp == 0) mbar_expect(fb, r >= 2 ? 16384 : 8192);
            if (warp < 2) bulk_g2s(sb + unit_off(22 + 2 * blk), src, 4096, fb);
            else {
              bulk_g2s(sb + unit_off(26 + 2 * blk), src + 4096, 2048, fb);
              bulk_g2s(sb + unit_off(13 + blk), src + 6144, 2048, fb);
            }
          }
          __syncwarp();
          mbar_wait(fb, it ? ((it - 1) & 1) : 0);
          uint32_t x = 1;
          if (r >= 2) x &= (lds_u32(ck + unit_off(22)) ^ epoch) & (lds_u32(cv) ^ epoch);
          if (r >= 1) x &= (lds_u32(ck + unit_off(24)) ^ epoch) & (lds_u32(cv - (threadIdx.x < 64 ? 4096 : 2048)) ^ epoch);
          uint32_t all;
          asm volatile("{\n.reg .pred p, q;\nsetp.ne.u32 p, %1, 0;\nbar.red.and.pred q, 5, 128, p;\nselp.u32 %0, 1, 0, q;\n}" : "=r"(all) : "r"(x) : "memory");
          if (all) break;
        }
        if (threadIdx.x == 0) mbar_arrive(bar + 8 * B_HVALID);
        __syncwarp();
      }
#pragma unroll
      for (int j = 0; j < 4; j++) {
        q[j] = pack2(acc[2 * j] * QSCALE, acc[2 * j + 1] * QSCALE); q1[j] = pack2(acc[8 + 2 * j] * QSCALE, acc[9 + 2 * j] * QSCALE);
        q2[j] = q3[j] = 0u;
      }
    }
    TCtx tc;
    const int nabs = r >= 2 ? 0 : (4 - 2 * r - wgi);
    tc.p0 = 2 * t4 > g; tc.p1 = 2 * t4 + 1 > g;
    tc.msk = (tc.p0 ? 0xFFFFu : 0u) | (tc.p1 ? 0xFFFF0000u : 0u);
    uint8_t* obp = scr->ob + (size_t)r * 131072 + c * 4096 + (row0 + g) * 16 + t4 * 4 - 32768;
    float SA[32], SB[32], O[12]; uint32_t PA[16], PB[16], fail = 0;
    zero_acc(O);
    const bool hsig = lane == 0 && warp == 0, esig = hsig;
    float g0 = 0.f, g1 = 0.f;
#pragma unroll 1
    for (uint32_t h = 0; h < 4; h++) {
      const uint32_t z16 = d16(sb + OFF_Z), b = h & 1;
      const uint32_t ka = z16 + (128u << 16) - 22 * 128 + b * (10 * 128), kb = z16 + (128u << 16) - 24 * 128 + b * (6 * 128);
      const uint32_t ko = z16 - tab(TAB_K0 >> 32, h) * 128 + ((h == 2 ? 128u : 256u) << 16);
      const uint32_t sa = (13 - 12 * b) * 128, sb_ = (14 - 11 * b) * 128, so = tab(TAB_VS >> 32, h) * 128;
      const uint32_t v0 = z16 + (8u << 16) + 64 * wgi, v1 = z16 + (8u << 16) + 64 - 64 * wgi;
#define KD(J) (J == 0 ? kdesc(ka, ka + 64, wgi) : J == 1 ? kdesc(ka + 64, kb, wgi) : J == 2 ? kdesc(kb, kb + 64, wgi) : J == 3 ? kdesc(kb + 64, ko, wgi) : kdesc(ko, ko + 64, wgi))
#define VD(J) vdesc(J < 2 ? sa : (J < 4 ? sb_ : so), J < 1 ? sa : (J < 3 ? sb_ : so), wgi, (J & 1) ? v1 : v0, J < nabs ? 0u : ~0u)
      wg_fence(); qk64(SA, q, KD(3)); wg_commit();
      if (wgi == 1) mbar_wait(bar + 8 * (h ? B_HFULL + (h & 1) : B_HVALID), h >> 1);
      wg_fence(); qk64(SB, q, KD(2)); wg_commit();
      wg_wait<1>();
      {
        if (hsig && (h == 1 || h == 2)) mbar_arrive(bar + 8 * (B_HEMPTY - 1 + h));
        if (esig && h == 3) mbar_arrive(bar + 8 * B_EFREE);
        uint4 v;
        const bool ok = normalize_head(O, g0, g1, v);
        store_head(ok && h > 0, v, obp, bar + 8 * (B_OPUB - 1 + h));
        fail |= (ok ? 0u : 1u) << h;
        obp += 32768;
      }
      TLW(5 + 2 * h + wgi);
      exp_pack32(SA, PA);
      { const uint64_t d = VD(3); PV4(O, PA, 0, d, d + 32); }
      qk64(SA, q, KD(1)); wg_commit();
      if (h == 1) {
        mbar_wait(bar + 8 * B_QREAD, 0);
        const uint4* qp = scr->q23 + bid * 512 + threadIdx.x;
        asm volatile("ld.relaxed.gpu.global.v4.u32 {%0,%1,%2,%3}, [%4];" : "=r"(q1[0]), "=r"(q1[1]), "=r"(q1[2]), "=r"(q1[3]) : "l"(qp) : "memory");
        asm volatile("ld.relaxed.gpu.global.v4.u32 {%0,%1,%2,%3}, [%4];" : "=r"(q2[0]), "=r"(q2[1]), "=r"(q2[2]), "=r"(q2[3]) : "l"(qp + 256) : "memory");
      }
      wg_wait<2>();
      exp_pack32(SB, PB);
      { const uint64_t d = VD(2); PV4(O, PB, 1, d, d + 32); }
      qk32<0>(SB, q, KD(0)); qk32<16>(SB, q, KD(4)); wg_commit();
      wg_wait<2>();
      exp_pack32(SA, PA);
      { const uint64_t d = VD(1); PV4(O, PA, 1, d, d + 32); }
      qk32<0>(SA, q, KD(0) + 32); qk32<16>(SA, q, KD(4) + 32); wg_commit();
      wg_wait<2>();
      merged_kstep<0, 0>(SB, PB, 0 - warp, tc); merged_kstep<8, 4>(SB, PB, 1 - warp, tc);
      PV4(O, PB, 1, VD(0), VD(4));
      wg_wait<1>();
      merged_kstep<0, 0>(SA, PA, 2 - warp, tc); merged_kstep<8, 4>(SA, PA, 3 - warp, tc);
      PV4(O, PA, 1, VD(0) + 32, VD(4) + 32);
      if (h == 0) {
        mbar_wait(bar + 8 * B_GREADY, 1);
        g0 = 1.f - lds_f32(sb + OFF_GTAB + (row0 + g) * 4); g1 = 1.f - lds_f32(sb + OFF_GTAB + (row0 + g + 8) * 4);
      }
      if (wgi == 0 && h < 3) mbar_wait(bar + 8 * (B_HFULL + ((h + 1) & 1)), (h + 1) >> 1);
      wg_wait<0>();
#pragma unroll
      for (int j = 0; j < 4; j++) { const uint32_t t = q[j]; q[j] = q1[j]; q1[j] = q2[j]; q2[j] = q3[j]; q3[j] = t; }
    }
    uint4 v;
    fail = __reduce_or_sync(0xffffffffu, (fail | (normalize_head(O, g0, g1, v) ? 0u : 16u)) >> 1);
    if (hsig) mbar_arrive(bar + 8 * B_TDONE);
    const uint32_t tm = t4 == 0 ? ~1u : ~0u, tb = t4 == 0 ? (~lds_u32(sb + OFF_EPOCH) & 1u) : 0u;
    uint32_t* const b3f = &scr->obf[((r * 4 + 3) * 2 + (c >> 2)) * 8];
    store_head(!(fail & 8), make_uint4((v.x & tm) | tb, (v.y & tm) | tb, (v.z & tm) | tb, (v.w & tm) | tb), obp, bar, false);
    if (lane == 0 && !(fail & 8)) red_relaxed(b3f, 1);
    if (__builtin_expect(fail != 0, 0)) {
#pragma unroll 1
      for (int h = 0; h < 4; h++) {
        if ((fail >> h) & 1) {
          const uint4 u = slow_head(scr, make_uint4(q[0], q[1], q[2], q[3]), r, c, h, row0, g0, g1);
          if (h < 3) store_head(true, u, obp + (h - 3) * 32768, bar + 8 * (B_OPUB + h));
          else { store_head(true, make_uint4((u.x & tm) | tb, (u.y & tm) | tb, (u.z & tm) | tb, (u.w & tm) | tb), obp, bar, false); if (lane == 0) red_relaxed(b3f, 1); }
        }
#pragma unroll
        for (int j = 0; j < 4; j++) { q[j] = q1[j]; q1[j] = q2[j]; q2[j] = q3[j]; }
      }
    }
    TLW(13 + wgi);
    const uint32_t ob = (wgi * 4 + warp + 6) & 7;
    {
      const uint32_t epoch = lds_u32(sb + OFF_EPOCH);
      const uint32_t o0 = sb + tile_off(ob, 0), o1 = sb + tile_off(ob, 1), o2 = sb + tile_off(ob, 2), o3 = sb + tile_off(ob, 3);
      const uint32_t ck = CHKG == 128 ? lane * 128 + (lane & 7) * 16 : lane * 64 + ((lane >> 1) & 3) * 16;
      const int ro = ((bid >> 4) << 1) | (c & 1);
      if (ob < 4) mbar_wait(bar + 8 * (ob < 2 ? B_KV1ST : B_OBEMPTY + ob), 1);
#pragma unroll 1
      for (uint32_t n = ob < 2 ? 12 + ob : (ob < 4 ? 4 + ob : (ob < 6 ? 6 + ob : 2 + ob)); n < ((ob & 6) == 2 ? 16u : 14u); n += 8) {
        TL(112 + n - 6);
        mbar_wait(bar + 8 * (B_OBFULL + ob), n < 8 ? 1 : 0);
        TL(96 + n);
#pragma unroll 1
        for (uint32_t it = 0; it < SPIN_LIMIT; it++) {
          uint32_t x = 1;
#pragma unroll
          for (int j = 0; j < 128 / CHKG; j++)
            x &= (lds_u32(o0 + ck + j * 2048) ^ epoch) & (lds_u32(o1 + ck + j * 2048) ^ epoch) & (lds_u32(o2 + ck + j * 2048) ^ epoch) & (lds_u32(o3 + ck + j * 2048) ^ epoch);
          if (__all_sync(0xffffffffu, x)) break;
          const uint8_t* src = is_b(n) ? scr->ob + (size_t)((ro * 4 + 3) * 2 + (n & 1)) * 16384 : scr->oa + (size_t)(ro * 8 + a_grp(n)) * 16384;
#pragma unroll 1
          for (uint32_t i = lane * 16; i < 16384; i += 512) {
            uint4 t;
            asm volatile("ld.relaxed.gpu.global.v4.u32 {%0,%1,%2,%3}, [%4];" : "=r"(t.x), "=r"(t.y), "=r"(t.z), "=r"(t.w) : "l"(src + i) : "memory");
            asm volatile("st.shared.v4.u32 [%0], {%1,%2,%3,%4};" :: "r"(sb + tile_off(ob, i >> 12) + (i & 4095)), "r"(t.x), "r"(t.y), "r"(t.z), "r"(t.w) : "memory");
          }
          fence_async_smem();
          __syncwarp();
        }
        if (lane == 0) mbar_arrive(bar + 8 * valid_bar(ob));
        TL(80 + n);
        __syncwarp();
      }
    }
  } else if (wg == 2) {
    asm volatile("setmaxnreg.inc.sync.aligned.u32 %0;" :: "n"(GREG));
    ROLE_IDS
    const int g = lane >> 2, t4 = lane & 3, tid = threadIdx.x & 127;
    GCtx gc; gc.bar = bar; gc.abar = map_cta(bar, warp == 0 ? rank : peer); gc.sig = tid == 0 || tid == 32; gc.arm = tid == 64; gc.osig = tid == 0;
    uint32_t epoch = 0;
    if (tid == 0) {
      epoch = ld_relaxed(&scr->epoch[0]);
      asm volatile("st.shared.u32 [%0], %1;" :: "r"(sb + OFF_EPOCH), "r"(epoch) : "memory");
    }
    {
      mbar_wait(bar + 8 * B_GATE, 0);
      float a0 = 0.f, a1 = 0.f;
      const uint32_t rw = c * 16 + (tid >> 3);
      const uint32_t xa = sb + OFF_X + rw * 128 + (((lane & 7) ^ (rw & 7)) << 4), ga = sb + OFF_Z + (lane & 7) * 16;
#pragma unroll 1
      for (uint32_t i = 0; i < 8; i += 2) {
        mbar_wait(bar + 8 * (B_XFULL + i), 0); mbar_wait(bar + 8 * (B_XFULL + i + 1), 0);
        a0 = dot8(lds128(xa + i * 16384), lds128(ga + i * 128), a0);
        a1 = dot8(lds128(xa + i * 16384 + 16384), lds128(ga + i * 128 + 128), a1);
      }
      a0 += a1;
      a0 += __shfl_xor_sync(0xffffffffu, a0, 1); a0 += __shfl_xor_sync(0xffffffffu, a0, 2); a0 += __shfl_xor_sync(0xffffffffu, a0, 4);
      if ((lane & 7) == 0) stg32(&scr->gate[r * 128 + rw], __float_as_uint(rcp(1.f + ex2(-LOG2E * a0))));
      named_sync(2, 128);
      asm volatile("st.shared.v4.u32 [%0], {%1,%1,%1,%1};" :: "r"(sb + OFF_Z + tid * 16), "r"(0x3F803F80u) : "memory");
      fence_async_smem();
      named_sync(2, 128);
      if (tid == 0) mbar_arrive(bar + 8 * B_GPUB);
    }
    TLW(16);
    epoch = lds_u32(sb + OFF_EPOCH);
    float acc[64], acc2[64];
    {
      float a0[48], a1[48];
      const uint32_t dx = (1u << 16) + d16(sb + OFF_X), dw = (256u << 16) + d16(sb);
      if (gc.sig) mbar_arrive_remote(gc.abar + 8 * (B_WEMPTY + 3));
      mbar_wait(bar + 8 * B_KVST, 0);
      wg_fence();
#pragma unroll
      for (int i = 0; i < 8; i++) {
        const uint32_t wo = ((i & 2) ? unit_off(6 + 6 * (i & 1)) : OFF_WR + (i & 1) * 12288) >> 4;
        mbar_wait(bar + 8 * (B_OBFULL + (i & 3)), i >> 2);
#pragma unroll
        for (int k = 0; k < 4; k++) {
          if (i | k) { mma96(a0, dx, i * 1024 + k * 2, dw, wo + k * 64); mma96(a1, dx, 512 + i * 1024 + k * 2, dw, wo + k * 64); }
          else { mma96<true>(a0, dx, 0, dw, wo); mma96<true>(a1, dx, 512, dw, wo); }
        }
        wg_commit();
        if (i >= 1 && i < 7) {
          wg_wait<1>();
          if (i <= 4) { if (gc.osig) mbar_arrive(bar + 8 * (B_OBEMPTY + i - 1)); }
          else if (gc.sig) {
            mbar_arrive_remote(gc.abar + 8 * (B_WEMPTY + i - 5));
            if (i == 6) mbar_arrive_remote(gc.abar + 8 * (B_WEMPTY + 2));
          }
        }
      }
      wg_wait<0>();
      TLW(17);
      named_sync(2, 128);
      if (tid == 0) mbar_arrive(bar + 8 * B_KV1ST);
      const uint32_t ra = sb + (warp * 16 + ((lane >> 3) & 1) * 8 + (lane & 7)) * 16;
      uint8_t* gp = scr->kvg + (size_t)(r * 8 + c) * 32768 + 16384 + (warp * 16 + g) * 16 + t4 * 4;
      uint4* qp = scr->q23 + bid * 512 + tid;
#define QFRAG(a, o) make_uint4(pack2(a[o] * QSCALE, a[o + 1] * QSCALE), pack2(a[o + 2] * QSCALE, a[o + 3] * QSCALE), pack2(a[o + 4] * QSCALE, a[o + 5] * QSCALE), pack2(a[o + 6] * QSCALE, a[o + 7] * QSCALE))
      g_pass<GPEND>(acc, sb, gc, [&](int i, int k) {
        if (k != 3) return;
        if (i == 0) { st_kv<2, 0>(a0, ra, lane >= 16); st_kv<3, 1>(a0, ra, lane >= 16); }
        if (i == 1) { st_kv<2, 0>(a1, ra + 1024, lane >= 16); st_kv<3, 1>(a1, ra + 1024, lane >= 16); fence_async_smem(); __syncwarp(); }
        if (i == 2) stg_kv<0, 8>(a0, gp);
        if (i == 3) stg_kv<0, 8>(a1, gp + 1024);
        if (i == 4) {
          qp[0] = QFRAG(a0, 0); qp[128] = QFRAG(a1, 0); qp[256] = QFRAG(a0, 8); qp[384] = QFRAG(a1, 8);
          __syncwarp();
          if (lane == 0) mbar_arrive(bar + 8 * B_QREAD);
          __syncwarp();
        }
      });
    }
    float4* kva = &scr->kva[epoch & 1][c * 4 + warp][0][lane];
    uint32_t pk[32];
    TLW(19);
    g_pass<GPEND>(acc2, sb, gc, [&](int i, int k) { pk[4 * i + k] = pack2(phi(acc[8 * i + 2 * k]), phi(acc[8 * i + 2 * k + 1])); });
    TLW(20);
    {
      float c0[4] = {0.f, 0.f, 0.f, 0.f}, c1[4] = {0.f, 0.f, 0.f, 0.f}, z0[4] = {0.f, 0.f, 0.f, 0.f};
#pragma unroll
      for (int i = 0; i < 8; i++) {
        uint32_t a0 = pack2(acc2[8 * i], acc2[8 * i + 1]), a1 = pack2(acc2[8 * i + 2], acc2[8 * i + 3]);
        uint32_t a2 = pack2(acc2[8 * i + 4], acc2[8 * i + 5]), a3 = pack2(acc2[8 * i + 6], acc2[8 * i + 7]);
        hmma(c0, a0, a1, a2, a3, pk[4 * i], pk[4 * i + 2]);
        hmma(c1, a0, a1, a2, a3, pk[4 * i + 1], pk[4 * i + 3]);
        hmma(z0, pk[4 * i], pk[4 * i + 1], pk[4 * i + 2], pk[4 * i + 3], 0x3F803F80u, 0x3F803F80u);
      }
      asm volatile("red.relaxed.gpu.global.add.v4.f32 [%0], {%1,%2,%3,%4};" :: "l"(kva), "f"(c0[0]), "f"(c0[1]), "f"(c1[0]), "f"(1.f) : "memory");
      asm volatile("red.relaxed.gpu.global.add.v4.f32 [%0], {%1,%2,%3,%4};" :: "l"(kva + 32), "f"(c1[1]), "f"(c0[2]), "f"(c0[3]), "f"(1.f) : "memory");
      asm volatile("red.relaxed.gpu.global.add.v4.f32 [%0], {%1,%2,%3,%4};" :: "l"(kva + 64), "f"(c1[2]), "f"(c1[3]), "f"(t4 ? z0[2] : z0[0]), "f"(1.f) : "memory");
    }
    TLW(21);
    g_pass_last<GPEND>(acc, sb, gc);
    TLW(22);
    float4 u0, u1, u2;
#define LD_KV() do { \
      asm volatile("ld.relaxed.gpu.global.v4.f32 {%0,%1,%2,%3}, [%4];" : "=f"(u0.x), "=f"(u0.y), "=f"(u0.z), "=f"(u0.w) : "l"(kva) : "memory"); \
      asm volatile("ld.relaxed.gpu.global.v4.f32 {%0,%1,%2,%3}, [%4];" : "=f"(u1.x), "=f"(u1.y), "=f"(u1.z), "=f"(u1.w) : "l"(kva + 32) : "memory"); \
      asm volatile("ld.relaxed.gpu.global.v4.f32 {%0,%1,%2,%3}, [%4];" : "=f"(u2.x), "=f"(u2.y), "=f"(u2.z), "=f"(u2.w) : "l"(kva + 64) : "memory"); } while (0)
    LD_KV();
    mbar_wait(bar + 8 * B_GREADY, 1);
#pragma unroll
    for (int j = 0; j < 32; j++) pk[j] = movm(pack2(phi(acc[2 * j]), phi(acc[2 * j + 1])));
    TLW(23);
#pragma unroll 1
    for (uint32_t it = 0; it < SPIN_LIMIT && !__all_sync(0xffffffffu, u0.w == 16.f && u1.w == 16.f && u2.w == 16.f); it++) LD_KV();
    TLW(24);
    {
      const uint32_t b00 = pack2(u0.x, u0.y), b01 = pack2(u0.z, u1.x), b10 = pack2(u1.y, u1.z), b11 = pack2(u2.x, u2.y);
      const uint32_t bz0 = pack2(__shfl_sync(0xffffffffu, u2.z, 8 * t4), __shfl_sync(0xffffffffu, u2.z, 8 * t4 + 4));
      const uint32_t bz1 = pack2(__shfl_sync(0xffffffffu, u2.z, 8 * t4 + 1), __shfl_sync(0xffffffffu, u2.z, 8 * t4 + 5));
      uint8_t* op = scr->oa + (size_t)((r * 8 + c) * 4 + warp) * 4096 + g * 16 + t4 * 4;
      const uint32_t tm = t4 == 0 ? ~1u : ~0u, tb = t4 == 0 ? (~epoch & 1u) : 0u;
#pragma unroll
      for (int m = 0; m < 8; m++) {
        float n0[4] = {0.f, 0.f, 0.f, 0.f}, n1[4] = {0.f, 0.f, 0.f, 0.f}, dn[4] = {0.f, 0.f, 0.f, 0.f};
        hmma(n0, pk[4 * m], pk[4 * m + 2], pk[4 * m + 1], pk[4 * m + 3], b00, b01);
        hmma(n1, pk[4 * m], pk[4 * m + 2], pk[4 * m + 1], pk[4 * m + 3], b10, b11);
        hmma(dn, pk[4 * m], pk[4 * m + 2], pk[4 * m + 1], pk[4 * m + 3], bz0, bz1);
        const float r0 = lds_f32(sb + OFF_GTAB + (16 * m + g) * 4) * rcp(dn[0] + 1e-6f);
        const float r1 = lds_f32(sb + OFF_GTAB + (16 * m + g + 8) * 4) * rcp(dn[2] + 1e-6f);
        stg32(op + m * 256, (pack2(n0[0] * r0, n0[1] * r0) & tm) | tb);
        stg32(op + m * 256 + 128, (pack2(n0[2] * r1, n0[3] * r1) & tm) | tb);
        stg32(op + m * 256 + 2048, (pack2(n1[0] * r0, n1[1] * r0) & tm) | tb);
        stg32(op + m * 256 + 2176, (pack2(n1[2] * r1, n1[3] * r1) & tm) | tb);
      }
      __syncwarp();
      if (lane == 0) red_relaxed(&scr->oaf[r * 8], 1);
      __syncwarp();
    }
    TLW(25);
    {
      const int ro = ((bid >> 4) << 1) | (c & 1);
      mbar_wait(bar + 8 * B_EFREE, 0);
      mbar_wait(bar + 8 * B_XFULL, 1); mbar_wait(bar + 8 * (B_XFULL + 1), 1); mbar_wait(bar + 8 * B_OBFULL, 0);
      out_steps<0>(acc, (1u << 16) + d16(sb + OFF_X), (128u << 16) + d16(sb), bar, gc TLPASS);
      wg_wait<0>();
      TR(t_om);
      named_sync(2, 128);
      const uint32_t rr = (lane >> 4) * 8 + (lane & 7);
      const uint32_t ra = sb + OFF_X + rr * 128 + (((2 * warp + ((lane >> 3) & 1)) ^ (lane & 7)) * 16);
#pragma unroll
      for (int j = 0; j < 16; j += 2)
        stsm4t(ra + j * 1024, pack2(acc[4 * j], acc[4 * j + 1]), pack2(acc[4 * j + 2], acc[4 * j + 3]),
               pack2(acc[4 * j + 4], acc[4 * j + 5]), pack2(acc[4 * j + 6], acc[4 * j + 7]));
      fence_async_smem();
      named_sync(2, 128);
      if (tid == 0) {
        tma2d_store(&tmOut, (c >> 1) * 128 + rank * 64, ro * 128, sb + OFF_X);
        asm volatile("cp.async.bulk.commit_group;\ncp.async.bulk.wait_group.read 0;" ::: "memory");
        if (blockIdx.x == 0) asm volatile("st.relaxed.gpu.global.u32 [%0], %1;" :: "l"(&scr->epoch[0]), "r"(epoch + 1) : "memory");
      }
      TLW(27); TW(26, t_om);
    }
  } else {
    asm volatile("setmaxnreg.dec.sync.aligned.u32 %0;" :: "n"(HREG));
    ROLE_IDS
    if (warp == 0) {
      if (lane == 0) {
#pragma unroll 1
        for (uint32_t n = 2; n < 4; n++) {
          mbar_expect(bar + 8 * (B_KVFULL + n), 12288);
          if ((n & 1) == (uint32_t)rank) tma3d_mc(sb + OFF_Z - (n + 1) * 12288, &tmWB, c * 64, n * 64, bar + 8 * (B_KVFULL + n));
          mbar_expect(bar + 8 * (B_XFULL + n), 16384);
          tma2d(sb + OFF_X + n * 16384, &tmX, n * 64, r * 128, bar + 8 * (B_XFULL + n));
        }
#pragma unroll 1
        for (uint32_t n = 0; n < 4; n++) {
          mbar_wait(bar + 8 * (B_KVFULL + XGATE(n)), 0);
          mbar_expect(bar + 8 * (B_XFULL + 4 + n), 16384);
          tma2d(sb + OFF_X + (4 + n) * 16384, &tmX, (4 + n) * 64, r * 128, bar + 8 * (B_XFULL + 4 + n));
        }
#pragma unroll 1
        for (uint32_t n = 0; n < 6; n++) {
          mbar_wait(bar + 8 * (B_KVEMPTY + (n & 3)), n >> 2);
          if (n < 4) {
            mbar_expect(bar + 8 * (B_KVFULL + n), 12288);
            if ((n & 1) == (uint32_t)rank) tma3d_mc(sb + OFF_Z - (n + 1) * 12288, &tmWB, c * 64, (n + 4) * 64, bar + 8 * (B_KVFULL + n));
          }
          if (n >= 2) {
            const uint32_t j = n - 2;
            mbar_expect(bar + 8 * (B_OBFULL + j), 12288);
            if ((j & 1) == (uint32_t)rank) tma3d_mc(sb + (j < 2 ? OFF_WR + j * 12288 : OFF_Z - (j - 1) * 12288), &tmWB, c * 64 + 32, j * 64, bar + 8 * (B_OBFULL + j));
          }
        }
        mbar_wait(bar + 8 * (B_WEMPTY + 3), 0);
        mbar_expect(bar + 8 * (B_WFULL + 3), 8192);
        if (rank == 1) tma2d_mc(sb + OFF_WR + 3 * 8192, &tmWA, 512 + c * 64, 3 * 64, bar + 8 * (B_WFULL + 3));
#pragma unroll 1
        for (uint32_t j = 0; j < 4; j++) {
          mbar_wait(bar + 8 * (B_OBEMPTY + j), 0);
          mbar_expect(bar + 8 * (B_OBFULL + j), 12288);
          tma3d(sb + (j < 2 ? OFF_WR + j * 12288 : OFF_Z - (j - 1) * 12288), &tmWB, c * 64 + 32, (j + 4) * 64, bar + 8 * (B_OBFULL + j));
        }
#pragma unroll 1
        for (uint32_t n = 0; n < 3; n++) {
          mbar_wait(bar + 8 * (B_WEMPTY + n), 0);
          mbar_expect(bar + 8 * (B_WFULL + n), 8192);
          if ((n & 1) == (uint32_t)rank) tma2d_mc(sb + OFF_WR + n * 8192, &tmWA, 512 + c * 64, n * 64, bar + 8 * (B_WFULL + n));
        }
#pragma unroll 1
        for (uint32_t j = 0; j < 5; j++) {
          const int col = (j == 0 ? 512 : j < 3 ? 1024 : 0) + c * 64, row = ((~j & 1) * 4 + rank) * 64;
          mbar_wait(bar + 8 * (B_WEMPTY + rank), ~j & 1);
          tma2d_mc(sb + OFF_WR + rank * 8192, &tmWA, col, row, bar + 8 * (B_WFULL + rank));
          mbar_wait(bar + 8 * (B_WEMPTY + rank + 2), ~j & 1);
          tma2d_mc(sb + OFF_WR + (rank + 2) * 8192, &tmWA, col, row + 128, bar + 8 * (B_WFULL + rank + 2));
        }
        mbar_wait(bar + 8 * (B_WEMPTY + 3), 1);
        const int ocol = (c >> 1) * 128 + rank * 64;
#pragma unroll 1
        for (uint32_t i = 0; i < 8; i++) {
          const uint32_t slot = i & 3;
          if (i >= 4) mbar_wait(bar + 8 * (B_WEMPTY + slot), 0);
          const CUtensorMap* tm = i < 4 ? &tmOB : &tmOA;
          mbar_expect(bar + 8 * (B_XFULL + i), 16384);
          tma2d(sb + OFF_X + i * 16384, tm, ocol, slot * 128, bar + 8 * (B_XFULL + i));
          tma2d(sb + OFF_X + i * 16384 + 8192, tm, ocol, slot * 128 + 64, bar + 8 * (B_XFULL + i));
        }
      }
    } else if (warp == 1) {
      if (lane == 0 && bid >= 64 && bid < 96) tma3d_prefetch(&tmWB, c * 64, (r - 4) * 64);
      mbar_wait(bar + 8 * (B_KVFULL + QPFG), 0);
      if (lane == 0 && bid < 64) tma3d_prefetch(&tmWB, c * 64 + 32, r * 64);
      mbar_wait(bar + 8 * B_EPOCH, 0);
      const uint32_t epoch = lds_u32(sb + OFF_EPOCH);
      if (r == 0) {
        float4* z = &scr->kva[(epoch + 1) & 1][c * 4][0][lane];
#pragma unroll 1
        for (int i = 0; i < 12; i++) z[i * 32] = make_float4(0.f, 0.f, 0.f, 0.f);
      }
      {
        const int blk = lane / 3, piece = lane - 3 * blk;
        const bool act = lane < 6 && (r - 2 + blk) >= 0;
        const uint32_t bytes = r >= 2 ? 16384 : r * 8192;
        const uint8_t* src = scr->kvg + (size_t)((r - 2 + blk) * 8 + c) * 32768 + (piece == 0 ? 0 : 2048 + piece * 2048);
#pragma unroll 1
        for (int h = 0; h < 4; h++) {
          const int b = h & 1;
          if (h == 0) { if (r < 2) mbar_wait(bar + 8 * B_KVST, 0); }
          else {
            if (act && piece == 0 && h < 3) poll_ge(&scr->kvf[((r - 2 + blk) * 8 + c) * 32 + 8 * (h - 1)], epoch + 1);
            mbar_wait(bar + 8 * (h == 1 ? B_KV1ST : B_HEMPTY + b), 0);
          }
          if (r < 2 && h < 2) {
            for (int bk = 0; bk < 2 - r; bk++) {
              const int s = 2 * b + bk;
              for (int i = lane; i < 384; i += 32)
                asm volatile("st.shared.v4.u32 [%0], {%1,%1,%1,%1};" :: "r"(sb + OFF_Z + (i < 256 ? i * 16 - tab(TAB_K0, s) * 2048 : (i - 256) * 16 - tab(TAB_VS, s) * 4096)), "r"(0u) : "memory");
            }
            fence_async_smem();
          }
          __syncwarp();
          if (lane == 0) mbar_expect(bar + 8 * (B_HFULL + b), bytes);
          __syncwarp();
          const int s = 2 * b + blk;
          const int pos = piece == 0 ? tab(TAB_K0, s & 3) : (piece == 1 ? 2 * tab(TAB_VS, s & 3) : tab(TAB_VS, s & 3));
          if (act && h > 0) bulk_g2s(sb + OFF_Z - pos * 2048, src + h * 8192, piece == 0 ? 4096 : 2048, bar + 8 * (B_HFULL + b));
          TL(56 + h);
        }
      }
    } else if (warp == 2) {
        if (lane == 0) {
        mbar_expect(bar + 8 * B_GATE, 1024);
        bulk_g2s(sb + OFF_Z, gate_w, 1024, bar + 8 * B_GATE);
      }
      mbar_wait(bar + 8 * (B_KVEMPTY + APFG), 0);
#pragma unroll
      for (int i = 0; i < 3; i++) prefetch_l2(wa + blockIdx.x * 12288 + i * 4096 + lane * 128);

      mbar_wait(bar + 8 * B_EPOCH, 0);
      const uint32_t epoch = lds_u32(sb + OFF_EPOCH);
      {
        if (lane == 0) poll_ge(&scr->gf[r * 8], (epoch + 1) * 8);
        __syncwarp();
        uint4 v;
        asm volatile("ld.relaxed.gpu.global.v4.u32 {%0,%1,%2,%3}, [%4];" : "=r"(v.x), "=r"(v.y), "=r"(v.z), "=r"(v.w) : "l"(&scr->gate[r * 128 + lane * 4]) : "memory");
        asm volatile("st.shared.v4.u32 [%0], {%1,%2,%3,%4};" :: "r"(sb + OFF_GTAB + lane * 16), "r"(v.x), "r"(v.y), "r"(v.z), "r"(v.w) : "memory");
        __syncwarp();
        if (lane == 0) mbar_arrive(bar + 8 * B_GREADY);
        TL(29);
      }
      mbar_wait(bar + 8 * B_HEMPTY, 0);
      prefetch_l2(wob + blockIdx.x * 4096 + lane * 128);
      prefetch_l2(woa + blockIdx.x * 4096 + lane * 128);
    } else {
      if (lane == 0) {
        mbar_wait(bar + 8 * B_KVST, 0);
        red_release(&scr->kvf[(r * 8 + c) * 32], 1);
        red_relaxed(&scr->gf[r * 8], 1);
        mbar_wait(bar + 8 * B_QREAD, 0);
        red_release(&scr->kvf[(r * 8 + c) * 32 + 8], 1);
        TS(83);
#pragma unroll 1
        for (uint32_t e = 0; e < 2; e++) {
          mbar_wait(bar + 8 * (B_OPUB + e), 0);
          red_release(&scr->obf[((r * 4 + e) * 2 + (c >> 2)) * 8], 1);
        }
      }
    }
    if (lane == 0) {
      const uint32_t epoch = lds_u32(sb + OFF_EPOCH);
#pragma unroll 1
      for (uint32_t n = warp == 3 ? 3 : 2 - warp; n < 16; n += 4) {
        fetch_o(scr, n, sb, ((bid >> 4) << 1) | (c & 1), epoch);
        if (n == 3) {
          mbar_wait(bar + 8 * (B_OPUB + 2), 0);
          red_release(&scr->obf[((r * 4 + 2) * 2 + (c >> 2)) * 8], 1);
        }
      }
    }
  }
}

typedef CUresult (*EncodeFn)(CUtensorMap*, CUtensorMapDataType, cuuint32_t, void*, const cuuint64_t*, const cuuint64_t*, const cuuint32_t*,
                             const cuuint32_t*, CUtensorMapInterleave, CUtensorMapSwizzle, CUtensorMapL2promotion, CUtensorMapFloatOOBfill);

void make_map(EncodeFn enc, CUtensorMap* tm, const void* p, uint64_t cols, uint64_t rows, uint32_t box_rows) {
  cuuint64_t gd[2] = {cols, rows};
  cuuint64_t gs[1] = {cols * 2};
  cuuint32_t bd[2] = {64, box_rows};
  cuuint32_t es[2] = {1, 1};
  enc(tm, CU_TENSOR_MAP_DATA_TYPE_BFLOAT16, 2, const_cast<void*>(p), gd, gs, bd, es, CU_TENSOR_MAP_INTERLEAVE_NONE,
      CU_TENSOR_MAP_SWIZZLE_128B, CU_TENSOR_MAP_L2_PROMOTION_L2_128B, CU_TENSOR_MAP_FLOAT_OOB_FILL_NONE);
}

}

extern "C" void kernel_launch(void* const* d_in, const int* in_sizes, int n_in, void* d_out, int out_size) {
  (void)in_sizes; (void)n_in; (void)out_size;
  EncodeFn enc = nullptr;
  cudaDriverEntryPointQueryResult qr;
  cudaGetDriverEntryPoint("cuTensorMapEncodeTiled", (void**)&enc, cudaEnableDefault, &qr);
  CUtensorMap tmX, tmWA, tmWB, tmOA, tmOB, tmOut;
  make_map(enc, &tmX, d_in[0], DM, SEQ, 128);
  make_map(enc, &tmWA, d_in[1], 3 * DM, DM, 64);
  make_map(enc, &tmOA, d_in[2], DM, DM, 64);
  {
    cuuint64_t gd[3] = {DM, DM, 3};
    cuuint64_t gs[2] = {3 * DM * 2, DM * 2};
    cuuint32_t bd[3] = {32, 64, 3}, es[3] = {1, 1, 1};
    CUresult e = enc(&tmWB, CU_TENSOR_MAP_DATA_TYPE_BFLOAT16, 3, d_in[4], gd, gs, bd, es, CU_TENSOR_MAP_INTERLEAVE_NONE,
        CU_TENSOR_MAP_SWIZZLE_64B, CU_TENSOR_MAP_L2_PROMOTION_L2_64B, CU_TENSOR_MAP_FLOAT_OOB_FILL_NONE);
    (void)e;
  }
  make_map(enc, &tmOB, d_in[5], DM, DM, 64);
  make_map(enc, &tmOut, d_out, DM, SEQ, 128);
  cudaFuncSetAttribute(fused_kernel, cudaFuncAttributeMaxDynamicSharedMemorySize, SMEM_BYTES);
  void* scr = nullptr;
  cudaGetSymbolAddress(&scr, g_scr);
  TLARG0
  fused_kernel<<<128, 512, SMEM_BYTES, cudaStreamPerThread>>>((Scratch*)scr, (const __nv_bfloat16*)d_in[6], (const uint8_t*)d_in[1],
      (const uint8_t*)d_in[2], (const uint8_t*)d_in[5] TLARG, tmX, tmWB, tmWA, tmOA, tmOB, tmOut);
}
```
